```python
import torch

def _softmax(x, axis=-1):
    return torch.softmax(x, dim=axis)
def _gelu(x):
    return torch.nn.functional.gelu(x, approximate="tanh")
def _silu(x):
    return torch.nn.functional.silu(x)
def _sigmoid(x):
    return torch.sigmoid(x)
def _layernorm(x, axis=-1, eps=1e-5):
    m = x.mean(dim=axis, keepdim=True)
    v = x.var(dim=axis, keepdim=True, unbiased=False)
    return (x - m) / torch.sqrt(v + eps)
def _scatter_add(tgt, idx, src, axis=0):
    return tgt.clone().index_add_(axis, idx, src)
def _segment_sum(src, seg, n):
    out = torch.zeros((n,) + src.shape[1:], dtype=src.dtype)
    return out.index_add_(0, seg, src)
def _pad(x, pw):
    flat = tuple(v for pair in reversed(pw) for v in pair)
    return torch.nn.functional.pad(x, flat)

kernel_name = 'standalone__embedding_ops__recsys'

def setup_inputs():

    _w = (lambda a: (lambda t: t.to(torch.bfloat16) if t.is_floating_point() else t)(torch.as_tensor(a)))
    B, D = 16384, 128
    L = max(20, 2)
    V = min(100000, 100000)
    lengths = torch.randint(1, L + 1, (B,) if isinstance(B, int) else B)
    nnz = int(lengths.sum())
    seg = torch.repeat_interleave(torch.arange(B), lengths).to(torch.int64)
    vals = (lambda lo, hi, *s: torch.randint(lo, hi, s))(0, V, nnz).to(torch.int64)
    return {
        "values": _w(vals),
        "seg_ids": _w(seg),
        "table": _w((lambda *s: torch.randn(*s, dtype=torch.bfloat16) * 0.05)(V, D)),
        "out0": _w((lambda *s: torch.randn(*s, dtype=torch.bfloat16) * 0.05)(B, D)),
    }

def reference(values, seg_ids, table, out0):
    emb = table[values]
    n_seg = out0.shape[0]
    pooled = _segment_sum(emb, seg_ids, n_seg)
    return pooled + out0
```

```cpp
#include <cuda_runtime.h>
#include <cuda_bf16.h>
#include <stdint.h>

constexpr int CQ = 22;
constexpr int MAXP = 123 * CQ / 4 * 4;
constexpr int HEAD_BYTES = 16512;
constexpr int REF_OFF = 33024;
constexpr int SMEM_BYTES = 90496;

#define FAST_PTX \
    "{\n" \
    ".reg .pred pa, pb, pc, ph, po, pd, pq, r<4>;\n" \
    ".reg .b32 tid, lane, it, hf, e, t0, t1, t2, t3, E, m, g, sh, eye, ps, ia, ib, sl, first, nb, col, wlo, fs, fr, mh, fb;\n" \
    ".reg .b32 v1, v2, s<3>, n<3>, M<3>, id<8>, x<32>, y<16>, z<12>, a<8>, h<8>;\n" \
    ".reg .b64 as, tb, ad, fo;\n" \
      \
    "mov.u32 tid, %%tid.x;\n" \
    "shr.u32 g, tid, 5;\n" \
    "mad.lo.s32 t3, g, -10, tid;\n" \
    "mad.lo.s32 t2, t3, 16, %10;\n" \
    "and.b32 t2, t2, -16;\n" \
    "min.u32 t1, t2, %14;\n" \
    "cvt.u64.u32 ad, t1;\n" \
    "add.s64 as, ad, %1;\n" \
    "ld.relaxed.cta.global.v4.u32 {z0,z1,z2,z3}, [as];\n" \
    "setp.ge.u32 pa, tid, 992;\n" \
    "vote.sync.any.pred pa, pa, -1;\n" \
    "@pa bra.uni SERVICE;\n" \
      \
    "mad.lo.s32 sh, tid, 16, %9;\n" \
    "and.b32 lane, tid, 31;\n" \
    "add.s32 e, %10, %8;\n" \
    "and.b32 e, e, -16;\n" \
    "add.s32 t0, t2, -16;\n" \
    "setp.gt.u32 r0, lane, 23;\n" \
    "selp.b32 t0, e, t0, r0;\n" \
    "min.u32 t0, t0, %14;\n" \
    "cvt.u64.u32 ad, t0;\n" \
    "add.s64 as, ad, %2;\n" \
    "cp.async.ca.shared.global [sh+49536], [as], 16;\n" \
    "cp.async.commit_group;\n" \
      \
    "shr.u32 t0, tid, 3;\n" \
    "and.b32 col, tid, 7;\n" \
    "mad.lo.s32 wlo, t0, 88, %10;\n" \
    "mul.lo.s32 ia, t0, 88;\n" \
    "add.s32 ia, ia, %9;\n" \
    "setp.lt.u32 pq, tid, %13;\n" \
    "setp.lt.and.s32 pq, wlo, %11, pq;\n" \
    "and.b32 t0, %10, 1;\n" \
    "mad.lo.s32 t0, t0, 8, col;\n" \
    "mad.wide.u32 tb, t0, 16, %3;\n" \
    "mad.lo.s32 t3, t3, 16, %9;\n" \
    "setp.lt.u32 r3, lane, 22;\n" \
    "vote.sync.any.pred pa, pq, -1;\n" \
    "@!pa bra.uni SKIP1;\n" \
      \
    "add.s32 t0, t2, 0;\n" \
    "setp.lt.s32 r0, t0, %11;\n" \
    "selp.b32 z0, z0, 0, r0;\n" \
    "add.s32 t0, t2, 4;\n" \
    "setp.lt.s32 r1, t0, %11;\n" \
    "selp.b32 z1, z1, 0, r1;\n" \
    "add.s32 t0, t2, 8;\n" \
    "setp.lt.s32 r2, t0, %11;\n" \
    "selp.b32 z2, z2, 0, r2;\n" \
    "add.s32 t0, t2, 12;\n" \
    "setp.lt.s32 pa, t0, %11;\n" \
    "selp.b32 z3, z3, 0, pa;\n" \
    "@r3 st.volatile.shared.v4.u32 [t3+33152], {z0,z1,z2,z3};\n" \
    "bar.warp.sync -1;\n" \
    "ld.volatile.shared.v2.u32 {id0,id1}, [ia+33152];\n" \
    "ld.volatile.shared.v2.u32 {id2,id3}, [ia+33160];\n" \
    "ld.volatile.shared.v2.u32 {id4,id5}, [ia+33168];\n" \
    "ld.volatile.shared.v2.u32 {id6,id7}, [ia+33176];\n" \
    "mul.wide.u32 ad, id0, 256;\n" \
    "add.s64 ad, tb, ad;\n" \
    "ld.global.nc.v4.u32 {x0,x1,x2,x3}, [ad];\n" \
    "mul.wide.u32 ad, id1, 256;\n" \
    "add.s64 ad, tb, ad;\n" \
    "ld.global.nc.v4.u32 {x4,x5,x6,x7}, [ad];\n" \
    "mul.wide.u32 ad, id2, 256;\n" \
    "add.s64 ad, tb, ad;\n" \
    "ld.global.nc.v4.u32 {x8,x9,x10,x11}, [ad];\n" \
    "mul.wide.u32 ad, id3, 256;\n" \
    "add.s64 ad, tb, ad;\n" \
    "ld.global.nc.v4.u32 {x12,x13,x14,x15}, [ad];\n" \
    "mul.wide.u32 ad, id4, 256;\n" \
    "add.s64 ad, tb, ad;\n" \
    "ld.global.nc.v4.u32 {x16,x17,x18,x19}, [ad];\n" \
    "mul.wide.u32 ad, id5, 256;\n" \
    "add.s64 ad, tb, ad;\n" \
    "ld.global.nc.v4.u32 {x20,x21,x22,x23}, [ad];\n" \
    "mul.wide.u32 ad, id6, 256;\n" \
    "add.s64 ad, tb, ad;\n" \
    "ld.global.nc.v4.u32 {x24,x25,x26,x27}, [ad];\n" \
    "mul.wide.u32 ad, id7, 256;\n" \
    "add.s64 ad, tb, ad;\n" \
    "ld.global.nc.v4.u32 {x28,x29,x30,x31}, [ad];\n" \
    "SKIP1:\n" \
      \
    "st.volatile.shared.v4.u32 [sh], {-1,-1,-1,-1};\n" \
    "st.volatile.shared.v4.u32 [sh+16512], {-1,-1,-1,-1};\n" \
    "mov.b64 {t0,t1}, tb;\n" \
    "shfl.sync.idx.b32 t0, t0, lane, 31, -1;\n" \
    "shfl.sync.idx.b32 t1, t1, lane, 31, -1;\n" \
    "mov.b64 tb, {t0,t1};\n" \
      \
    "cp.async.wait_group 0;\n" \
    "bar.warp.sync -1;\n" \
    "mad.lo.s32 ia, col, 4, ia;\n" \
    "mad.lo.s32 t1, g, 160, ia;\n" \
    "mad.lo.s32 hf, col, 4, wlo;\n" \
    "or.b32 e, e, 15;\n" \
    "min.u32 t0, e, %11;\n" \
    "add.s32 t0, t0, -1;\n" \
    "and.b32 t0, t0, 12;\n" \
    "mad.lo.s32 ib, lane, -16, sh;\n" \
    "add.s32 ib, ib, t0;\n" \
    "ld.volatile.shared.u32 s0, [t1+49548];\n" \
    "ld.volatile.shared.u32 n0, [t1+49552];\n" \
    "ld.volatile.shared.u32 s1, [t1+49580];\n" \
    "ld.volatile.shared.u32 n1, [t1+49584];\n" \
    "ld.volatile.shared.u32 s2, [t1+49612];\n" \
    "ld.volatile.shared.u32 n2, [t1+49616];\n" \
    "ld.volatile.shared.u32 v1, [ia+33184];\n" \
    "ld.volatile.shared.u32 v2, [ia+33216];\n" \
    "ld.volatile.shared.u32 sl, [ib+49920];\n" \
    "add.s32 t3, hf, -4;\n" \
    "setp.ge.u32 r0, t3, %11;\n" \
    "setp.ge.s32 r1, t3, %6;\n" \
    "setp.ge.s32 r2, t3, %12;\n" \
    "setp.ge.s32 pa, hf, %11;\n" \
    "setp.ge.s32 pb, hf, %6;\n" \
    "setp.ge.s32 pd, hf, %12;\n" \
    "shr.s32 t0, t3, 31;\n" \
    "or.b32 t0, t0, %7;\n" \
    "selp.b32 s0, t0, s0, r0;\n" \
    "selp.b32 s1, %7, s1, r1;\n" \
    "selp.b32 s2, %7, s2, r2;\n" \
    "selp.b32 n0, %7, n0, pa;\n" \
    "selp.b32 n1, %7, n1, pb;\n" \
    "selp.b32 n2, %7, n2, pd;\n" \
    "bar.sync 0, 1024;\n" \
      \
    "shr.u32 t0, lane, 2;\n" \
    "and.b32 t1, lane, 3;\n" \
    "shl.b32 t1, t1, 1;\n" \
    "sub.s32 t0, t0, t1;\n" \
    "shl.b32 t0, t0, 4;\n" \
    "shl.b32 eye, 0x3F80, t0;\n" \
    "ld.shared.u32 it, [%9+33024];\n" \
      \
    "setp.le.and.s32 pa, s0, sl, pq;\n" \
    "setp.ne.and.s32 pa, s0, n0, pa;\n" \
    "vote.sync.ballot.b32 M0, pa, -1;\n" \
    "setp.le.s32 pa, n1, sl;\n" \
    "selp.b32 v1, v1, 0, pa;\n" \
    "setp.le.and.s32 pa, s1, sl, pq;\n" \
    "setp.ne.and.s32 pa, s1, n1, pa;\n" \
    "vote.sync.ballot.b32 M1, pa, -1;\n" \
    "setp.le.s32 pa, n2, sl;\n" \
    "selp.b32 v2, v2, 0, pa;\n" \
    "setp.le.and.s32 pa, s2, sl, pq;\n" \
    "setp.ne.and.s32 pa, s2, n2, pa;\n" \
    "vote.sync.ballot.b32 M2, pa, -1;\n" \
    "shr.u32 fr, lane, 3;\n" \
    "mad.lo.s32 t3, fr, 0x11, 0x40;\n" \
    "prmt.b32 t0, M0, M1, t3;\n" \
    "mad.lo.s32 t3, fr, 0x100, 0x410;\n" \
    "prmt.b32 m, t0, M2, t3;\n" \
    "and.b32 t0, m, 1;\n" \
    "setp.eq.u32 ph, t0, 0;\n" \
    "and.b32 t0, m, 0x400000;\n" \
    "setp.eq.u32 po, t0, 0;\n" \
    "and.b32 m, m, 0x3ffffe;\n" \
      \
    "shfl.sync.idx.b32 fb, s2, 6, 0x181f, -1;\n" \
    "setp.le.and.s32 pd, fb, sl, pq;\n" \
    "neg.s32 t0, m;\n" \
    "and.b32 t0, t0, m;\n" \
    "selp.b32 mh, t0, 0, ph;\n" \
    "setp.eq.and.u32 ph, m, 0, ph;\n" \
    "and.pred ph, ph, pd;\n" \
    "and.pred po, po, pd;\n" \
      \
    "shfl.sync.idx.b32 t1, s2, 30, 31, -1;\n" \
    "min.s32 t1, t1, sl;\n" \
    "shfl.sync.idx.b32 first, s0, 0, 31, -1;\n" \
    "sub.s32 nb, t1, first;\n" \
    "add.s32 first, first, 1;\n" \
    "shfl.sync.idx.b32 t0, s0, 1, 0x181f, -1;\n" \
    "sub.s32 t0, t0, sl;\n" \
    "mad.lo.s32 t0, t0, 8, col;\n" \
    "mad.lo.s32 ps, t0, 16, %9;\n" \
    "sub.s32 t2, first, sl;\n" \
    "min.s32 t2, t2, 1;\n" \
    "mad.lo.s32 t2, t2, 8, lane;\n" \
    "mad.lo.s32 fs, t2, 16, %9;\n" \
    "add.s32 first, first, fr;\n" \
    "sub.s32 fr, nb, fr;\n" \
      \
    "sub.s32 t0, n0, s0;\n" \
    "sub.s32 t1, n1, s1;\n" \
    "max.s32 t0, t0, t1;\n" \
    "sub.s32 t1, n2, s2;\n" \
    "max.s32 t0, t0, t1;\n" \
    "setp.gt.s32 pa, t0, 1;\n" \
    "sub.s32 t0, sl, first;\n" \
    "setp.ge.or.s32 pa, t0, 319, pa;\n" \
    "setp.gt.and.s32 pb, wlo, e, po;\n" \
    "or.pred pa, pa, pb;\n" \
    "and.pred pa, pa, pq;\n" \
    "setp.ne.or.u32 pa, it, %10, pa;\n" \
    "mov.u32 t0, m;\n" \
    "@pa or.b32 t0, t0, 0x80000000;\n" \
    "@pq or.b32 t0, t0, 0x40000000;\n" \
    "setp.gt.s32 pa, nb, 12;\n" \
    "@pa or.b32 t0, t0, 0x20000000;\n" \
    "setp.gt.s32 pa, nb, 8;\n" \
    "@pa or.b32 t0, t0, 0x08000000;\n" \
    "setp.ge.or.u32 pa, mh, 0x20000, ph;\n" \
    "@pa or.b32 t0, t0, 0x10000000;\n" \
    "redux.sync.or.b32 E, t0, -1;\n" \
    "shr.u32 %0, E, 31;\n" \
    "setp.lt.s32 pa, E, 0x40000000;\n" \
    "@pa bra.uni END;\n" \
    "setp.ge.s32 pa, E, 0x60000000;\n" \
    "@pa bra.uni STAGE;\n" \
    "STAGED:\n" \
    "mov.u32 g, 2;\n" \
    "shfl.sync.idx.b32 ia, v1, 0, 0x181f, -1;\n" \
    "shfl.sync.idx.b32 ib, v1, 1, 0x181f, -1;\n" \
    "mov.u32 a0, 0;\n" \
    "mov.u32 a1, 0;\n" \
    "mov.u32 a2, 0;\n" \
    "mov.u32 a3, 0;\n" \
    "mov.u32 a4, 0;\n" \
    "mov.u32 a5, 0;\n" \
    "mov.u32 a6, 0;\n" \
    "mov.u32 a7, 0;\n" \
      \
    "LOOP:\n" \
    "mma.sync.aligned.m16n8k8.row.col.f32.bf16.bf16.f32 {a0,a1,a2,a3}, {x0,x1}, {eye}, {a0,a1,a2,a3};\n" \
    "mma.sync.aligned.m16n8k8.row.col.f32.bf16.bf16.f32 {a4,a5,a6,a7}, {x2,x3}, {eye}, {a4,a5,a6,a7};\n" \
    "mul.wide.u32 ad, ia, 256;\n" \
    "add.s64 ad, tb, ad;\n" \
    "@pq ld.global.nc.v4.u32 {x0,x1,x2,x3}, [ad];\n" \
    "shfl.sync.idx.b32 ia, v1, 2, 0x181f, -1;\n" \
    "and.b32 t0, E, 2;\n" \
    "setp.ne.u32 pa, t0, 0;\n" \
    "@pa bra.uni LF0;\n" \
    "KF0:\n" \
    "mma.sync.aligned.m16n8k8.row.col.f32.bf16.bf16.f32 {a0,a1,a2,a3}, {x4,x5}, {eye}, {a0,a1,a2,a3};\n" \
    "mma.sync.aligned.m16n8k8.row.col.f32.bf16.bf16.f32 {a4,a5,a6,a7}, {x6,x7}, {eye}, {a4,a5,a6,a7};\n" \
    "mul.wide.u32 ad, ib, 256;\n" \
    "add.s64 ad, tb, ad;\n" \
    "@pq ld.global.nc.v4.u32 {x4,x5,x6,x7}, [ad];\n" \
    "shfl.sync.idx.b32 ib, v1, 3, 0x181f, -1;\n" \
    "and.b32 t0, E, 4;\n" \
    "setp.ne.u32 pa, t0, 0;\n" \
    "@pa bra.uni LF1;\n" \
    "KF1:\n" \
    "mma.sync.aligned.m16n8k8.row.col.f32.bf16.bf16.f32 {a0,a1,a2,a3}, {x8,x9}, {eye}, {a0,a1,a2,a3};\n" \
    "mma.sync.aligned.m16n8k8.row.col.f32.bf16.bf16.f32 {a4,a5,a6,a7}, {x10,x11}, {eye}, {a4,a5,a6,a7};\n" \
    "mul.wide.u32 ad, ia, 256;\n" \
    "add.s64 ad, tb, ad;\n" \
    "@pq ld.global.nc.v4.u32 {x8,x9,x10,x11}, [ad];\n" \
    "shfl.sync.idx.b32 ia, v1, 4, 0x181f, -1;\n" \
    "and.b32 t0, E, 8;\n" \
    "setp.ne.u32 pa, t0, 0;\n" \
    "@pa bra.uni LF2;\n" \
    "KF2:\n" \
    "mma.sync.aligned.m16n8k8.row.col.f32.bf16.bf16.f32 {a0,a1,a2,a3}, {x12,x13}, {eye}, {a0,a1,a2,a3};\n" \
    "mma.sync.aligned.m16n8k8.row.col.f32.bf16.bf16.f32 {a4,a5,a6,a7}, {x14,x15}, {eye}, {a4,a5,a6,a7};\n" \
    "mul.wide.u32 ad, ib, 256;\n" \
    "add.s64 ad, tb, ad;\n" \
    "@pq ld.global.nc.v4.u32 {x12,x13,x14,x15}, [ad];\n" \
    "shfl.sync.idx.b32 ib, v1, 5, 0x181f, -1;\n" \
    "and.b32 t0, E, 16;\n" \
    "setp.ne.u32 pa, t0, 0;\n" \
    "@pa bra.uni LF3;\n" \
    "KF3:\n" \
    "mma.sync.aligned.m16n8k8.row.col.f32.bf16.bf16.f32 {a0,a1,a2,a3}, {x16,x17}, {eye}, {a0,a1,a2,a3};\n" \
    "mma.sync.aligned.m16n8k8.row.col.f32.bf16.bf16.f32 {a4,a5,a6,a7}, {x18,x19}, {eye}, {a4,a5,a6,a7};\n" \
    "mul.wide.u32 ad, ia, 256;\n" \
    "add.s64 ad, tb, ad;\n" \
    "@pq ld.global.nc.v4.u32 {x16,x17,x18,x19}, [ad];\n" \
    "shfl.sync.idx.b32 ia, v1, 6, 0x181f, -1;\n" \
    "and.b32 t0, E, 32;\n" \
    "setp.ne.u32 pa, t0, 0;\n" \
    "@pa bra.uni LF4;\n" \
    "KF4:\n" \
    "mma.sync.aligned.m16n8k8.row.col.f32.bf16.bf16.f32 {a0,a1,a2,a3}, {x20,x21}, {eye}, {a0,a1,a2,a3};\n" \
    "mma.sync.aligned.m16n8k8.row.col.f32.bf16.bf16.f32 {a4,a5,a6,a7}, {x22,x23}, {eye}, {a4,a5,a6,a7};\n" \
    "mul.wide.u32 ad, ib, 256;\n" \
    "add.s64 ad, tb, ad;\n" \
    "@pq ld.global.nc.v4.u32 {x20,x21,x22,x23}, [ad];\n" \
    "shfl.sync.idx.b32 ib, v1, 7, 0x181f, -1;\n" \
    "and.b32 t0, E, 64;\n" \
    "setp.ne.u32 pa, t0, 0;\n" \
    "@pa bra.uni LF5;\n" \
    "KF5:\n" \
    "setp.eq.u32 pa, g, 1;\n" \
    "@pa bra.uni LEAVE;\n" \
    "mma.sync.aligned.m16n8k8.row.col.f32.bf16.bf16.f32 {a0,a1,a2,a3}, {x24,x25}, {eye}, {a0,a1,a2,a3};\n" \
    "mma.sync.aligned.m16n8k8.row.col.f32.bf16.bf16.f32 {a4,a5,a6,a7}, {x26,x27}, {eye}, {a4,a5,a6,a7};\n" \
    "mul.wide.u32 ad, ia, 256;\n" \
    "add.s64 ad, tb, ad;\n" \
    "@pq ld.global.nc.v4.u32 {x24,x25,x26,x27}, [ad];\n" \
    "shfl.sync.idx.b32 ia, v2, 0, 0x181f, -1;\n" \
    "and.b32 t0, E, 128;\n" \
    "setp.ne.u32 pa, t0, 0;\n" \
    "@pa bra.uni LF6;\n" \
    "KF6:\n" \
    "mma.sync.aligned.m16n8k8.row.col.f32.bf16.bf16.f32 {a0,a1,a2,a3}, {x28,x29}, {eye}, {a0,a1,a2,a3};\n" \
    "mma.sync.aligned.m16n8k8.row.col.f32.bf16.bf16.f32 {a4,a5,a6,a7}, {x30,x31}, {eye}, {a4,a5,a6,a7};\n" \
    "mul.wide.u32 ad, ib, 256;\n" \
    "add.s64 ad, tb, ad;\n" \
    "@pq ld.global.nc.v4.u32 {x28,x29,x30,x31}, [ad];\n" \
    "shfl.sync.idx.b32 ib, v2, 1, 0x181f, -1;\n" \
    "and.b32 t0, E, 256;\n" \
    "setp.ne.u32 pa, t0, 0;\n" \
    "@pa bra.uni LF7;\n" \
    "KF7:\n" \
    "shr.u32 mh, mh, 8;\n" \
    "shr.u32 E, E, 8;\n" \
    "shr.u32 m, m, 8;\n" \
    "mov.u32 v1, v2;\n" \
    "add.s32 g, g, -1;\n" \
    "bra.uni LOOP;\n" \
      \
    "LEAVE:\n" \
    "sub.s64 fo, tb, %3;\n" \
    "mul.wide.s32 ad, first, 256;\n" \
    "add.s64 fo, fo, ad;\n" \
    "add.s64 ad, fo, %4;\n" \
    "mma.sync.aligned.m16n8k8.row.col.f32.bf16.bf16.f32 {a0,a1,a2,a3}, {x24,x25}, {eye}, {a0,a1,a2,a3};\n" \
    "mma.sync.aligned.m16n8k8.row.col.f32.bf16.bf16.f32 {a4,a5,a6,a7}, {x26,x27}, {eye}, {a4,a5,a6,a7};\n" \
    "mov.u32 y0, 0;\n" \
    "mov.u32 y1, 0;\n" \
    "mov.u32 y2, 0;\n" \
    "mov.u32 y3, 0;\n" \
    "setp.gt.s32 pa, fr, 0;\n" \
    "@pa ld.volatile.global.v4.u32 {y0,y1,y2,y3}, [ad+0];\n" \
    "and.b32 t0, E, 128;\n" \
    "setp.ne.u32 pa, t0, 0;\n" \
    "@pa bra.uni LH6;\n" \
    "KH6:\n" \
    "mma.sync.aligned.m16n8k8.row.col.f32.bf16.bf16.f32 {a0,a1,a2,a3}, {x28,x29}, {eye}, {a0,a1,a2,a3};\n" \
    "mma.sync.aligned.m16n8k8.row.col.f32.bf16.bf16.f32 {a4,a5,a6,a7}, {x30,x31}, {eye}, {a4,a5,a6,a7};\n" \
    "mov.u32 y4, 0;\n" \
    "mov.u32 y5, 0;\n" \
    "mov.u32 y6, 0;\n" \
    "mov.u32 y7, 0;\n" \
    "setp.gt.s32 pa, fr, 4;\n" \
    "@pa ld.volatile.global.v4.u32 {y4,y5,y6,y7}, [ad+1024];\n" \
    "and.b32 t0, E, 256;\n" \
    "setp.ne.u32 pa, t0, 0;\n" \
    "@pa bra.uni LH7;\n" \
    "KH7:\n" \
    "mov.u32 y8, 0;\n" \
    "mov.u32 y9, 0;\n" \
    "mov.u32 y10, 0;\n" \
    "mov.u32 y11, 0;\n" \
    "setp.gt.s32 pa, fr, 8;\n" \
    "@pa ld.volatile.global.v4.u32 {y8,y9,y10,y11}, [ad+2048];\n" \
    "sub.s64 fo, ad, %4;\n" \
    "add.s64 fo, fo, %5;\n" \
      \
    "bar.warp.sync -1;\n" \
    "add.s32 t0, %9, 16256;\n" \
    "selp.b32 ia, sh, t0, po;\n" \
    "ld.volatile.shared.u32 t0, [ia+128];\n" \
    "ld.volatile.shared.u32 t1, [ia+16640];\n" \
    "max.u32 t0, t0, t1;\n" \
    "and.b32 t1, E, 0x100000;\n" \
    "setp.ne.u32 pa, t1, 0;\n" \
    "setp.eq.or.u32 pa, t0, 0xffffffff, pa;\n" \
    "vote.sync.any.pred pa, pa, -1;\n" \
    "@pa bra.uni GENERAL;\n" \
    "mma.sync.aligned.m16n8k8.row.col.f32.bf16.bf16.f32 {a0,a1,a2,a3}, {x0,x1}, {eye}, {a0,a1,a2,a3};\n" \
    "mma.sync.aligned.m16n8k8.row.col.f32.bf16.bf16.f32 {a4,a5,a6,a7}, {x2,x3}, {eye}, {a4,a5,a6,a7};\n" \
    "and.b32 t0, E, 512;\n" \
    "setp.ne.u32 pa, t0, 0;\n" \
    "@pa bra.uni LQ0;\n" \
    "KQ0:\n" \
    "mma.sync.aligned.m16n8k8.row.col.f32.bf16.bf16.f32 {a0,a1,a2,a3}, {x4,x5}, {eye}, {a0,a1,a2,a3};\n" \
    "mma.sync.aligned.m16n8k8.row.col.f32.bf16.bf16.f32 {a4,a5,a6,a7}, {x6,x7}, {eye}, {a4,a5,a6,a7};\n" \
    "ld.volatile.shared.v4.u32 {h0,h1,h2,h3}, [ia+128];\n" \
    "ld.volatile.shared.v4.u32 {h4,h5,h6,h7}, [ia+16640];\n" \
    "and.b32 t0, E, 1024;\n" \
    "setp.ne.u32 pa, t0, 0;\n" \
    "@pa bra.uni LQ1;\n" \
    "KQ1:\n" \
    "mma.sync.aligned.m16n8k8.row.col.f32.bf16.bf16.f32 {a0,a1,a2,a3}, {x8,x9}, {eye}, {a0,a1,a2,a3};\n" \
    "mma.sync.aligned.m16n8k8.row.col.f32.bf16.bf16.f32 {a4,a5,a6,a7}, {x10,x11}, {eye}, {a4,a5,a6,a7};\n" \
    "and.b32 t0, E, 2048;\n" \
    "setp.ne.u32 pa, t0, 0;\n" \
    "@pa bra.uni LQ2;\n" \
    "KQ2:\n" \
    "mma.sync.aligned.m16n8k8.row.col.f32.bf16.bf16.f32 {a0,a1,a2,a3}, {x12,x13}, {eye}, {a0,a1,a2,a3};\n" \
    "mma.sync.aligned.m16n8k8.row.col.f32.bf16.bf16.f32 {a4,a5,a6,a7}, {x14,x15}, {eye}, {a4,a5,a6,a7};\n" \
    "mma.sync.aligned.m16n8k8.row.col.f32.bf16.bf16.f32 {h0,h1,h2,h3}, {x20,x21}, {eye}, {h0,h1,h2,h3};\n" \
    "mma.sync.aligned.m16n8k8.row.col.f32.bf16.bf16.f32 {h4,h5,h6,h7}, {x22,x23}, {eye}, {h4,h5,h6,h7};\n" \
    "and.b32 t0, E, 4096;\n" \
    "setp.ne.u32 pa, t0, 0;\n" \
    "@pa bra.uni LQ3;\n" \
    "KQ3:\n" \
    "mma.sync.aligned.m16n8k8.row.col.f32.bf16.bf16.f32 {a0,a1,a2,a3}, {x16,x17}, {eye}, {a0,a1,a2,a3};\n" \
    "mma.sync.aligned.m16n8k8.row.col.f32.bf16.bf16.f32 {a4,a5,a6,a7}, {x18,x19}, {eye}, {a4,a5,a6,a7};\n" \
    "and.b32 t0, E, 8192;\n" \
    "setp.ne.u32 pa, t0, 0;\n" \
    "@pa bra.uni LQ4;\n" \
    "KQ4:\n" \
    "add.f32 h0, a0, h0;\n" \
    "add.f32 h1, a1, h1;\n" \
    "add.f32 h2, a2, h2;\n" \
    "add.f32 h3, a3, h3;\n" \
    "add.f32 h4, a4, h4;\n" \
    "add.f32 h5, a5, h5;\n" \
    "add.f32 h6, a6, h6;\n" \
    "add.f32 h7, a7, h7;\n" \
    "cvt.rn.bf16x2.f32 t0, h1, h0;\n" \
    "cvt.rn.bf16x2.f32 t1, h3, h2;\n" \
    "cvt.rn.bf16x2.f32 t2, h5, h4;\n" \
    "cvt.rn.bf16x2.f32 t3, h7, h6;\n" \
    "@pd st.volatile.shared.v4.u32 [ps+73984], {t0,t1,t2,t3};\n" \
    "bar.warp.sync -1;\n" \
    "setp.gt.s32 r0, fr, 0;\n" \
    "setp.gt.s32 r1, fr, 4;\n" \
    "setp.gt.s32 r2, fr, 8;\n" \
    "ld.volatile.shared.v4.u32 {z0,z1,z2,z3}, [fs+73984];\n" \
    "ld.volatile.shared.v4.u32 {z4,z5,z6,z7}, [fs+74496];\n" \
    "@r2 ld.volatile.shared.v4.u32 {x16,x17,x18,x19}, [fs+75008];\n" \
    "and.b32 ib, E, 0x80000;\n" \
    "setp.ne.u32 pa, ib, 0;\n" \
    "and.b32 ib, E, 0x200000;\n" \
    "setp.ne.u32 pb, ib, 0;\n" \
    "add.rn.bf16x2 z0, z0, y0;\n" \
    "add.rn.bf16x2 z1, z1, y1;\n" \
    "add.rn.bf16x2 z2, z2, y2;\n" \
    "add.rn.bf16x2 z3, z3, y3;\n" \
    "@r0 st.global.v4.u32 [fo+0], {z0,z1,z2,z3};\n" \
    "add.rn.bf16x2 z4, z4, y4;\n" \
    "add.rn.bf16x2 z5, z5, y5;\n" \
    "add.rn.bf16x2 z6, z6, y6;\n" \
    "add.rn.bf16x2 z7, z7, y7;\n" \
    "@r1 st.global.v4.u32 [fo+1024], {z4,z5,z6,z7};\n" \
    "@!pa exit;\n" \
    "add.rn.bf16x2 z8, x16, y8;\n" \
    "add.rn.bf16x2 z9, x17, y9;\n" \
    "add.rn.bf16x2 z10, x18, y10;\n" \
    "add.rn.bf16x2 z11, x19, y11;\n" \
    "@r2 st.global.v4.u32 [fo+2048], {z8,z9,z10,z11};\n" \
    "@!pb exit;\n" \
    "bra.uni EXTRA;\n" \
      \
    "GENERAL:\n" \
    "mma.sync.aligned.m16n8k8.row.col.f32.bf16.bf16.f32 {a0,a1,a2,a3}, {x0,x1}, {eye}, {a0,a1,a2,a3};\n" \
    "mma.sync.aligned.m16n8k8.row.col.f32.bf16.bf16.f32 {a4,a5,a6,a7}, {x2,x3}, {eye}, {a4,a5,a6,a7};\n" \
    "and.b32 t0, E, 512;\n" \
    "setp.ne.u32 pa, t0, 0;\n" \
    "@pa bra.uni LG0;\n" \
    "KG0:\n" \
    "mma.sync.aligned.m16n8k8.row.col.f32.bf16.bf16.f32 {a0,a1,a2,a3}, {x4,x5}, {eye}, {a0,a1,a2,a3};\n" \
    "mma.sync.aligned.m16n8k8.row.col.f32.bf16.bf16.f32 {a4,a5,a6,a7}, {x6,x7}, {eye}, {a4,a5,a6,a7};\n" \
    "and.b32 t0, E, 1024;\n" \
    "setp.ne.u32 pa, t0, 0;\n" \
    "@pa bra.uni LG1;\n" \
    "KG1:\n" \
    "mma.sync.aligned.m16n8k8.row.col.f32.bf16.bf16.f32 {a0,a1,a2,a3}, {x8,x9}, {eye}, {a0,a1,a2,a3};\n" \
    "mma.sync.aligned.m16n8k8.row.col.f32.bf16.bf16.f32 {a4,a5,a6,a7}, {x10,x11}, {eye}, {a4,a5,a6,a7};\n" \
    "and.b32 t0, E, 2048;\n" \
    "setp.ne.u32 pa, t0, 0;\n" \
    "@pa bra.uni LG2;\n" \
    "KG2:\n" \
    "mma.sync.aligned.m16n8k8.row.col.f32.bf16.bf16.f32 {a0,a1,a2,a3}, {x12,x13}, {eye}, {a0,a1,a2,a3};\n" \
    "mma.sync.aligned.m16n8k8.row.col.f32.bf16.bf16.f32 {a4,a5,a6,a7}, {x14,x15}, {eye}, {a4,a5,a6,a7};\n" \
    "and.b32 t0, E, 4096;\n" \
    "setp.ne.u32 pa, t0, 0;\n" \
    "@pa bra.uni LG3;\n" \
    "KG3:\n" \
    "mma.sync.aligned.m16n8k8.row.col.f32.bf16.bf16.f32 {a0,a1,a2,a3}, {x16,x17}, {eye}, {a0,a1,a2,a3};\n" \
    "mma.sync.aligned.m16n8k8.row.col.f32.bf16.bf16.f32 {a4,a5,a6,a7}, {x18,x19}, {eye}, {a4,a5,a6,a7};\n" \
    "and.b32 t0, E, 8192;\n" \
    "setp.ne.u32 pa, t0, 0;\n" \
    "@pa bra.uni LG4;\n" \
    "KG4:\n" \
    "mov.u32 g, 0x10000000;\n" \
    "bar.warp.sync -1;\n" \
    "ld.volatile.shared.v4.u32 {h0,h1,h2,h3}, [ia+128];\n" \
    "ld.volatile.shared.v4.u32 {h4,h5,h6,h7}, [ia+16640];\n" \
    "mma.sync.aligned.m16n8k8.row.col.f32.bf16.bf16.f32 {a0,a1,a2,a3}, {x20,x21}, {eye}, {a0,a1,a2,a3};\n" \
    "mma.sync.aligned.m16n8k8.row.col.f32.bf16.bf16.f32 {a4,a5,a6,a7}, {x22,x23}, {eye}, {a4,a5,a6,a7};\n" \
    "FIN:\n" \
    "setp.ne.and.u32 pa, h0, 0xffffffff, pd;\n" \
    "setp.ne.and.u32 pa, h4, 0xffffffff, pa;\n" \
    "add.f32 h0, h0, a0;\n" \
    "add.f32 h1, h1, a1;\n" \
    "add.f32 h2, h2, a2;\n" \
    "add.f32 h3, h3, a3;\n" \
    "add.f32 h4, h4, a4;\n" \
    "add.f32 h5, h5, a5;\n" \
    "add.f32 h6, h6, a6;\n" \
    "add.f32 h7, h7, a7;\n" \
    "cvt.rn.bf16x2.f32 t0, h1, h0;\n" \
    "cvt.rn.bf16x2.f32 t1, h3, h2;\n" \
    "cvt.rn.bf16x2.f32 t2, h5, h4;\n" \
    "cvt.rn.bf16x2.f32 t3, h7, h6;\n" \
    "and.pred pb, pa, ph;\n" \
    "xor.pred pc, pa, pb;\n" \
    "xor.pred pd, pd, pa;\n" \
    "@pc st.volatile.shared.v4.u32 [ps+73984], {t0,t1,t2,t3};\n" \
    "or.pred pa, pd, ph;\n" \
    "vote.sync.any.pred pa, pa, -1;\n" \
    "@pa bra.uni RETRY;\n" \
    "FINEND:\n" \
    "bar.warp.sync -1;\n" \
    "setp.gt.s32 r0, fr, 0;\n" \
    "setp.gt.s32 r1, fr, 4;\n" \
    "setp.gt.s32 r2, fr, 8;\n" \
    "ld.volatile.shared.v4.u32 {z0,z1,z2,z3}, [fs+73984];\n" \
    "ld.volatile.shared.v4.u32 {z4,z5,z6,z7}, [fs+74496];\n" \
    "@r2 ld.volatile.shared.v4.u32 {x16,x17,x18,x19}, [fs+75008];\n" \
    "and.b32 ib, E, 0x80000;\n" \
    "setp.ne.u32 pa, ib, 0;\n" \
    "and.b32 ib, E, 0x200000;\n" \
    "setp.ne.u32 pb, ib, 0;\n" \
    "add.rn.bf16x2 z0, z0, y0;\n" \
    "add.rn.bf16x2 z1, z1, y1;\n" \
    "add.rn.bf16x2 z2, z2, y2;\n" \
    "add.rn.bf16x2 z3, z3, y3;\n" \
    "@r0 st.global.v4.u32 [fo+0], {z0,z1,z2,z3};\n" \
    "add.rn.bf16x2 z4, z4, y4;\n" \
    "add.rn.bf16x2 z5, z5, y5;\n" \
    "add.rn.bf16x2 z6, z6, y6;\n" \
    "add.rn.bf16x2 z7, z7, y7;\n" \
    "@r1 st.global.v4.u32 [fo+1024], {z4,z5,z6,z7};\n" \
    "@!pa exit;\n" \
    "add.rn.bf16x2 z8, x16, y8;\n" \
    "add.rn.bf16x2 z9, x17, y9;\n" \
    "add.rn.bf16x2 z10, x18, y10;\n" \
    "add.rn.bf16x2 z11, x19, y11;\n" \
    "@r2 st.global.v4.u32 [fo+2048], {z8,z9,z10,z11};\n" \
    "@!pb exit;\n" \
      \
    "EXTRA:\n" \
    "mov.u32 %0, 0;\n" \
    "mov.u32 g, 12;\n" \
    "cp.async.wait_all;\n" \
    "ld.shared.v4.u32 {y12,y13,y14,y15}, [sh+74112];\n" \
    "OUT1:\n" \
    "setp.gt.s32 pa, fr, g;\n" \
    "mad.lo.s32 t0, g, 128, fs;\n" \
    "mul.wide.u32 ad, g, 256;\n" \
    "add.s64 ad, ad, fo;\n" \
    "@pa ld.shared.v4.u32 {y4,y5,y6,y7}, [t0+73984];\n" \
    "add.rn.bf16x2 y12, y4, y12;\n" \
    "add.rn.bf16x2 y13, y5, y13;\n" \
    "add.rn.bf16x2 y14, y6, y14;\n" \
    "add.rn.bf16x2 y15, y7, y15;\n" \
    "@pa st.global.v4.u32 [ad], {y12,y13,y14,y15};\n" \
    "add.s32 g, g, 4;\n" \
    "setp.gt.s32 pa, fr, g;\n" \
    "vote.sync.any.pred pb, pa, -1;\n" \
    "@!pb bra.uni END;\n" \
    "sub.s64 ad, ad, %5;\n" \
    "add.s64 ad, ad, %4;\n" \
    "@pa ld.global.nc.v4.u32 {y12,y13,y14,y15}, [ad+1024];\n" \
    "bra.uni OUT1;\n" \
    "RETRY:\n" \
    "@pb st.volatile.shared.v4.u32 [sh], {h0,h1,h2,h3};\n" \
    "@pb st.volatile.shared.v4.u32 [sh+16512], {h4,h5,h6,h7};\n" \
    "xor.pred ph, ph, pb;\n" \
    "add.s32 g, g, -1;\n" \
    "setp.le.s32 pa, g, 0;\n" \
    "@pa bra.uni FINEND;\n" \
    "bar.warp.sync -1;\n" \
    "ld.volatile.shared.v4.u32 {h0,h1,h2,h3}, [ia+128];\n" \
    "ld.volatile.shared.v4.u32 {h4,h5,h6,h7}, [ia+16640];\n" \
    "bra.uni FIN;\n" \
      \
    "LF0:\n" \
    "and.b32 t0, m, 2;\n" \
    "setp.ne.u32 pa, t0, 0;\n" \
    "and.b32 t0, mh, 2;\n" \
    "setp.ne.u32 pb, t0, 0;\n" \
    "lop3.b32 t0, m, mh, 2, 0x20;\n" \
    "setp.ne.u32 pc, t0, 0;\n" \
    "@pb st.volatile.shared.v4.u32 [sh], {a0,a1,a2,a3};\n" \
    "@pb st.volatile.shared.v4.u32 [sh+16512], {a4,a5,a6,a7};\n" \
    "cvt.rn.bf16x2.f32 t0, a1, a0;\n" \
    "cvt.rn.bf16x2.f32 t1, a3, a2;\n" \
    "cvt.rn.bf16x2.f32 t2, a5, a4;\n" \
    "cvt.rn.bf16x2.f32 t3, a7, a6;\n" \
    "@pc st.volatile.shared.v4.u32 [ps+73984], {t0,t1,t2,t3};\n" \
    "@pa mov.u32 a0, 0;\n" \
    "@pa mov.u32 a1, 0;\n" \
    "@pa mov.u32 a2, 0;\n" \
    "@pa mov.u32 a3, 0;\n" \
    "@pa mov.u32 a4, 0;\n" \
    "@pa mov.u32 a5, 0;\n" \
    "@pa mov.u32 a6, 0;\n" \
    "@pa mov.u32 a7, 0;\n" \
    "@pa add.s32 ps, ps, 128;\n" \
    "bra.uni KF0;\n" \
    "LF1:\n" \
    "and.b32 t0, m, 4;\n" \
    "setp.ne.u32 pa, t0, 0;\n" \
    "and.b32 t0, mh, 4;\n" \
    "setp.ne.u32 pb, t0, 0;\n" \
    "lop3.b32 t0, m, mh, 4, 0x20;\n" \
    "setp.ne.u32 pc, t0, 0;\n" \
    "@pb st.volatile.shared.v4.u32 [sh], {a0,a1,a2,a3};\n" \
    "@pb st.volatile.shared.v4.u32 [sh+16512], {a4,a5,a6,a7};\n" \
    "cvt.rn.bf16x2.f32 t0, a1, a0;\n" \
    "cvt.rn.bf16x2.f32 t1, a3, a2;\n" \
    "cvt.rn.bf16x2.f32 t2, a5, a4;\n" \
    "cvt.rn.bf16x2.f32 t3, a7, a6;\n" \
    "@pc st.volatile.shared.v4.u32 [ps+73984], {t0,t1,t2,t3};\n" \
    "@pa mov.u32 a0, 0;\n" \
    "@pa mov.u32 a1, 0;\n" \
    "@pa mov.u32 a2, 0;\n" \
    "@pa mov.u32 a3, 0;\n" \
    "@pa mov.u32 a4, 0;\n" \
    "@pa mov.u32 a5, 0;\n" \
    "@pa mov.u32 a6, 0;\n" \
    "@pa mov.u32 a7, 0;\n" \
    "@pa add.s32 ps, ps, 128;\n" \
    "bra.uni KF1;\n" \
    "LF2:\n" \
    "and.b32 t0, m, 8;\n" \
    "setp.ne.u32 pa, t0, 0;\n" \
    "and.b32 t0, mh, 8;\n" \
    "setp.ne.u32 pb, t0, 0;\n" \
    "lop3.b32 t0, m, mh, 8, 0x20;\n" \
    "setp.ne.u32 pc, t0, 0;\n" \
    "@pb st.volatile.shared.v4.u32 [sh], {a0,a1,a2,a3};\n" \
    "@pb st.volatile.shared.v4.u32 [sh+16512], {a4,a5,a6,a7};\n" \
    "cvt.rn.bf16x2.f32 t0, a1, a0;\n" \
    "cvt.rn.bf16x2.f32 t1, a3, a2;\n" \
    "cvt.rn.bf16x2.f32 t2, a5, a4;\n" \
    "cvt.rn.bf16x2.f32 t3, a7, a6;\n" \
    "@pc st.volatile.shared.v4.u32 [ps+73984], {t0,t1,t2,t3};\n" \
    "@pa mov.u32 a0, 0;\n" \
    "@pa mov.u32 a1, 0;\n" \
    "@pa mov.u32 a2, 0;\n" \
    "@pa mov.u32 a3, 0;\n" \
    "@pa mov.u32 a4, 0;\n" \
    "@pa mov.u32 a5, 0;\n" \
    "@pa mov.u32 a6, 0;\n" \
    "@pa mov.u32 a7, 0;\n" \
    "@pa add.s32 ps, ps, 128;\n" \
    "bra.uni KF2;\n" \
    "LF3:\n" \
    "and.b32 t0, m, 16;\n" \
    "setp.ne.u32 pa, t0, 0;\n" \
    "and.b32 t0, mh, 16;\n" \
    "setp.ne.u32 pb, t0, 0;\n" \
    "lop3.b32 t0, m, mh, 16, 0x20;\n" \
    "setp.ne.u32 pc, t0, 0;\n" \
    "@pb st.volatile.shared.v4.u32 [sh], {a0,a1,a2,a3};\n" \
    "@pb st.volatile.shared.v4.u32 [sh+16512], {a4,a5,a6,a7};\n" \
    "cvt.rn.bf16x2.f32 t0, a1, a0;\n" \
    "cvt.rn.bf16x2.f32 t1, a3, a2;\n" \
    "cvt.rn.bf16x2.f32 t2, a5, a4;\n" \
    "cvt.rn.bf16x2.f32 t3, a7, a6;\n" \
    "@pc st.volatile.shared.v4.u32 [ps+73984], {t0,t1,t2,t3};\n" \
    "@pa mov.u32 a0, 0;\n" \
    "@pa mov.u32 a1, 0;\n" \
    "@pa mov.u32 a2, 0;\n" \
    "@pa mov.u32 a3, 0;\n" \
    "@pa mov.u32 a4, 0;\n" \
    "@pa mov.u32 a5, 0;\n" \
    "@pa mov.u32 a6, 0;\n" \
    "@pa mov.u32 a7, 0;\n" \
    "@pa add.s32 ps, ps, 128;\n" \
    "bra.uni KF3;\n" \
    "LF4:\n" \
    "and.b32 t0, m, 32;\n" \
    "setp.ne.u32 pa, t0, 0;\n" \
    "and.b32 t0, mh, 32;\n" \
    "setp.ne.u32 pb, t0, 0;\n" \
    "lop3.b32 t0, m, mh, 32, 0x20;\n" \
    "setp.ne.u32 pc, t0, 0;\n" \
    "@pb st.volatile.shared.v4.u32 [sh], {a0,a1,a2,a3};\n" \
    "@pb st.volatile.shared.v4.u32 [sh+16512], {a4,a5,a6,a7};\n" \
    "cvt.rn.bf16x2.f32 t0, a1, a0;\n" \
    "cvt.rn.bf16x2.f32 t1, a3, a2;\n" \
    "cvt.rn.bf16x2.f32 t2, a5, a4;\n" \
    "cvt.rn.bf16x2.f32 t3, a7, a6;\n" \
    "@pc st.volatile.shared.v4.u32 [ps+73984], {t0,t1,t2,t3};\n" \
    "@pa mov.u32 a0, 0;\n" \
    "@pa mov.u32 a1, 0;\n" \
    "@pa mov.u32 a2, 0;\n" \
    "@pa mov.u32 a3, 0;\n" \
    "@pa mov.u32 a4, 0;\n" \
    "@pa mov.u32 a5, 0;\n" \
    "@pa mov.u32 a6, 0;\n" \
    "@pa mov.u32 a7, 0;\n" \
    "@pa add.s32 ps, ps, 128;\n" \
    "bra.uni KF4;\n" \
    "LF5:\n" \
    "and.b32 t0, m, 64;\n" \
    "setp.ne.u32 pa, t0, 0;\n" \
    "and.b32 t0, mh, 64;\n" \
    "setp.ne.u32 pb, t0, 0;\n" \
    "lop3.b32 t0, m, mh, 64, 0x20;\n" \
    "setp.ne.u32 pc, t0, 0;\n" \
    "@pb st.volatile.shared.v4.u32 [sh], {a0,a1,a2,a3};\n" \
    "@pb st.volatile.shared.v4.u32 [sh+16512], {a4,a5,a6,a7};\n" \
    "cvt.rn.bf16x2.f32 t0, a1, a0;\n" \
    "cvt.rn.bf16x2.f32 t1, a3, a2;\n" \
    "cvt.rn.bf16x2.f32 t2, a5, a4;\n" \
    "cvt.rn.bf16x2.f32 t3, a7, a6;\n" \
    "@pc st.volatile.shared.v4.u32 [ps+73984], {t0,t1,t2,t3};\n" \
    "@pa mov.u32 a0, 0;\n" \
    "@pa mov.u32 a1, 0;\n" \
    "@pa mov.u32 a2, 0;\n" \
    "@pa mov.u32 a3, 0;\n" \
    "@pa mov.u32 a4, 0;\n" \
    "@pa mov.u32 a5, 0;\n" \
    "@pa mov.u32 a6, 0;\n" \
    "@pa mov.u32 a7, 0;\n" \
    "@pa add.s32 ps, ps, 128;\n" \
    "bra.uni KF5;\n" \
    "LF6:\n" \
    "and.b32 t0, m, 128;\n" \
    "setp.ne.u32 pa, t0, 0;\n" \
    "and.b32 t0, mh, 128;\n" \
    "setp.ne.u32 pb, t0, 0;\n" \
    "lop3.b32 t0, m, mh, 128, 0x20;\n" \
    "setp.ne.u32 pc, t0, 0;\n" \
    "@pb st.volatile.shared.v4.u32 [sh], {a0,a1,a2,a3};\n" \
    "@pb st.volatile.shared.v4.u32 [sh+16512], {a4,a5,a6,a7};\n" \
    "cvt.rn.bf16x2.f32 t0, a1, a0;\n" \
    "cvt.rn.bf16x2.f32 t1, a3, a2;\n" \
    "cvt.rn.bf16x2.f32 t2, a5, a4;\n" \
    "cvt.rn.bf16x2.f32 t3, a7, a6;\n" \
    "@pc st.volatile.shared.v4.u32 [ps+73984], {t0,t1,t2,t3};\n" \
    "@pa mov.u32 a0, 0;\n" \
    "@pa mov.u32 a1, 0;\n" \
    "@pa mov.u32 a2, 0;\n" \
    "@pa mov.u32 a3, 0;\n" \
    "@pa mov.u32 a4, 0;\n" \
    "@pa mov.u32 a5, 0;\n" \
    "@pa mov.u32 a6, 0;\n" \
    "@pa mov.u32 a7, 0;\n" \
    "@pa add.s32 ps, ps, 128;\n" \
    "bra.uni KF6;\n" \
    "LF7:\n" \
    "and.b32 t0, m, 256;\n" \
    "setp.ne.u32 pa, t0, 0;\n" \
    "and.b32 t0, mh, 256;\n" \
    "setp.ne.u32 pb, t0, 0;\n" \
    "lop3.b32 t0, m, mh, 256, 0x20;\n" \
    "setp.ne.u32 pc, t0, 0;\n" \
    "@pb st.volatile.shared.v4.u32 [sh], {a0,a1,a2,a3};\n" \
    "@pb st.volatile.shared.v4.u32 [sh+16512], {a4,a5,a6,a7};\n" \
    "cvt.rn.bf16x2.f32 t0, a1, a0;\n" \
    "cvt.rn.bf16x2.f32 t1, a3, a2;\n" \
    "cvt.rn.bf16x2.f32 t2, a5, a4;\n" \
    "cvt.rn.bf16x2.f32 t3, a7, a6;\n" \
    "@pc st.volatile.shared.v4.u32 [ps+73984], {t0,t1,t2,t3};\n" \
    "@pa mov.u32 a0, 0;\n" \
    "@pa mov.u32 a1, 0;\n" \
    "@pa mov.u32 a2, 0;\n" \
    "@pa mov.u32 a3, 0;\n" \
    "@pa mov.u32 a4, 0;\n" \
    "@pa mov.u32 a5, 0;\n" \
    "@pa mov.u32 a6, 0;\n" \
    "@pa mov.u32 a7, 0;\n" \
    "@pa add.s32 ps, ps, 128;\n" \
    "bra.uni KF7;\n" \
    "LH6:\n" \
    "and.b32 t0, m, 128;\n" \
    "setp.ne.u32 pa, t0, 0;\n" \
    "and.b32 t0, mh, 128;\n" \
    "setp.ne.u32 pb, t0, 0;\n" \
    "lop3.b32 t0, m, mh, 128, 0x20;\n" \
    "setp.ne.u32 pc, t0, 0;\n" \
    "@pb st.volatile.shared.v4.u32 [sh], {a0,a1,a2,a3};\n" \
    "@pb st.volatile.shared.v4.u32 [sh+16512], {a4,a5,a6,a7};\n" \
    "cvt.rn.bf16x2.f32 t0, a1, a0;\n" \
    "cvt.rn.bf16x2.f32 t1, a3, a2;\n" \
    "cvt.rn.bf16x2.f32 t2, a5, a4;\n" \
    "cvt.rn.bf16x2.f32 t3, a7, a6;\n" \
    "@pc st.volatile.shared.v4.u32 [ps+73984], {t0,t1,t2,t3};\n" \
    "@pa mov.u32 a0, 0;\n" \
    "@pa mov.u32 a1, 0;\n" \
    "@pa mov.u32 a2, 0;\n" \
    "@pa mov.u32 a3, 0;\n" \
    "@pa mov.u32 a4, 0;\n" \
    "@pa mov.u32 a5, 0;\n" \
    "@pa mov.u32 a6, 0;\n" \
    "@pa mov.u32 a7, 0;\n" \
    "@pa add.s32 ps, ps, 128;\n" \
    "bra.uni KH6;\n" \
    "LH7:\n" \
    "and.b32 t0, m, 256;\n" \
    "setp.ne.u32 pa, t0, 0;\n" \
    "and.b32 t0, mh, 256;\n" \
    "setp.ne.u32 pb, t0, 0;\n" \
    "lop3.b32 t0, m, mh, 256, 0x20;\n" \
    "setp.ne.u32 pc, t0, 0;\n" \
    "@pb st.volatile.shared.v4.u32 [sh], {a0,a1,a2,a3};\n" \
    "@pb st.volatile.shared.v4.u32 [sh+16512], {a4,a5,a6,a7};\n" \
    "cvt.rn.bf16x2.f32 t0, a1, a0;\n" \
    "cvt.rn.bf16x2.f32 t1, a3, a2;\n" \
    "cvt.rn.bf16x2.f32 t2, a5, a4;\n" \
    "cvt.rn.bf16x2.f32 t3, a7, a6;\n" \
    "@pc st.volatile.shared.v4.u32 [ps+73984], {t0,t1,t2,t3};\n" \
    "@pa mov.u32 a0, 0;\n" \
    "@pa mov.u32 a1, 0;\n" \
    "@pa mov.u32 a2, 0;\n" \
    "@pa mov.u32 a3, 0;\n" \
    "@pa mov.u32 a4, 0;\n" \
    "@pa mov.u32 a5, 0;\n" \
    "@pa mov.u32 a6, 0;\n" \
    "@pa mov.u32 a7, 0;\n" \
    "@pa add.s32 ps, ps, 128;\n" \
    "bra.uni KH7;\n" \
    "LQ0:\n" \
    "and.b32 t0, m, 512;\n" \
    "setp.ne.u32 pa, t0, 0;\n" \
    "cvt.rn.bf16x2.f32 t0, a1, a0;\n" \
    "cvt.rn.bf16x2.f32 t1, a3, a2;\n" \
    "cvt.rn.bf16x2.f32 t2, a5, a4;\n" \
    "cvt.rn.bf16x2.f32 t3, a7, a6;\n" \
    "@pa st.volatile.shared.v4.u32 [ps+73984], {t0,t1,t2,t3};\n" \
    "@pa mov.u32 a0, 0;\n" \
    "@pa mov.u32 a1, 0;\n" \
    "@pa mov.u32 a2, 0;\n" \
    "@pa mov.u32 a3, 0;\n" \
    "@pa mov.u32 a4, 0;\n" \
    "@pa mov.u32 a5, 0;\n" \
    "@pa mov.u32 a6, 0;\n" \
    "@pa mov.u32 a7, 0;\n" \
    "@pa add.s32 ps, ps, 128;\n" \
    "bra.uni KQ0;\n" \
    "LQ1:\n" \
    "and.b32 t0, m, 1024;\n" \
    "setp.ne.u32 pa, t0, 0;\n" \
    "cvt.rn.bf16x2.f32 t0, a1, a0;\n" \
    "cvt.rn.bf16x2.f32 t1, a3, a2;\n" \
    "cvt.rn.bf16x2.f32 t2, a5, a4;\n" \
    "cvt.rn.bf16x2.f32 t3, a7, a6;\n" \
    "@pa st.volatile.shared.v4.u32 [ps+73984], {t0,t1,t2,t3};\n" \
    "@pa mov.u32 a0, 0;\n" \
    "@pa mov.u32 a1, 0;\n" \
    "@pa mov.u32 a2, 0;\n" \
    "@pa mov.u32 a3, 0;\n" \
    "@pa mov.u32 a4, 0;\n" \
    "@pa mov.u32 a5, 0;\n" \
    "@pa mov.u32 a6, 0;\n" \
    "@pa mov.u32 a7, 0;\n" \
    "@pa add.s32 ps, ps, 128;\n" \
    "bra.uni KQ1;\n" \
    "LQ2:\n" \
    "and.b32 t0, m, 2048;\n" \
    "setp.ne.u32 pa, t0, 0;\n" \
    "cvt.rn.bf16x2.f32 t0, a1, a0;\n" \
    "cvt.rn.bf16x2.f32 t1, a3, a2;\n" \
    "cvt.rn.bf16x2.f32 t2, a5, a4;\n" \
    "cvt.rn.bf16x2.f32 t3, a7, a6;\n" \
    "@pa st.volatile.shared.v4.u32 [ps+73984], {t0,t1,t2,t3};\n" \
    "@pa mov.u32 a0, 0;\n" \
    "@pa mov.u32 a1, 0;\n" \
    "@pa mov.u32 a2, 0;\n" \
    "@pa mov.u32 a3, 0;\n" \
    "@pa mov.u32 a4, 0;\n" \
    "@pa mov.u32 a5, 0;\n" \
    "@pa mov.u32 a6, 0;\n" \
    "@pa mov.u32 a7, 0;\n" \
    "@pa add.s32 ps, ps, 128;\n" \
    "bra.uni KQ2;\n" \
    "LQ3:\n" \
    "and.b32 t0, m, 4096;\n" \
    "setp.ne.u32 pa, t0, 0;\n" \
    "cvt.rn.bf16x2.f32 t0, a1, a0;\n" \
    "cvt.rn.bf16x2.f32 t1, a3, a2;\n" \
    "cvt.rn.bf16x2.f32 t2, a5, a4;\n" \
    "cvt.rn.bf16x2.f32 t3, a7, a6;\n" \
    "@pa st.volatile.shared.v4.u32 [ps+73984], {t0,t1,t2,t3};\n" \
    "@pa mov.u32 a0, 0;\n" \
    "@pa mov.u32 a1, 0;\n" \
    "@pa mov.u32 a2, 0;\n" \
    "@pa mov.u32 a3, 0;\n" \
    "@pa mov.u32 a4, 0;\n" \
    "@pa mov.u32 a5, 0;\n" \
    "@pa mov.u32 a6, 0;\n" \
    "@pa mov.u32 a7, 0;\n" \
    "@pa add.s32 ps, ps, 128;\n" \
    "bra.uni KQ3;\n" \
    "LQ4:\n" \
    "and.b32 t0, m, 8192;\n" \
    "setp.ne.u32 pa, t0, 0;\n" \
    "cvt.rn.bf16x2.f32 t0, a1, a0;\n" \
    "cvt.rn.bf16x2.f32 t1, a3, a2;\n" \
    "cvt.rn.bf16x2.f32 t2, a5, a4;\n" \
    "cvt.rn.bf16x2.f32 t3, a7, a6;\n" \
    "@pa st.volatile.shared.v4.u32 [ps+73984], {t0,t1,t2,t3};\n" \
    "@pa mov.u32 a0, 0;\n" \
    "@pa mov.u32 a1, 0;\n" \
    "@pa mov.u32 a2, 0;\n" \
    "@pa mov.u32 a3, 0;\n" \
    "@pa mov.u32 a4, 0;\n" \
    "@pa mov.u32 a5, 0;\n" \
    "@pa mov.u32 a6, 0;\n" \
    "@pa mov.u32 a7, 0;\n" \
    "@pa add.s32 ps, ps, 128;\n" \
    "bra.uni KQ4;\n" \
    "LG0:\n" \
    "and.b32 t0, m, 512;\n" \
    "setp.ne.u32 pa, t0, 0;\n" \
    "and.b32 t0, mh, 512;\n" \
    "setp.ne.u32 pb, t0, 0;\n" \
    "lop3.b32 t0, m, mh, 512, 0x20;\n" \
    "setp.ne.u32 pc, t0, 0;\n" \
    "@pb st.volatile.shared.v4.u32 [sh], {a0,a1,a2,a3};\n" \
    "@pb st.volatile.shared.v4.u32 [sh+16512], {a4,a5,a6,a7};\n" \
    "cvt.rn.bf16x2.f32 t0, a1, a0;\n" \
    "cvt.rn.bf16x2.f32 t1, a3, a2;\n" \
    "cvt.rn.bf16x2.f32 t2, a5, a4;\n" \
    "cvt.rn.bf16x2.f32 t3, a7, a6;\n" \
    "@pc st.volatile.shared.v4.u32 [ps+73984], {t0,t1,t2,t3};\n" \
    "@pa mov.u32 a0, 0;\n" \
    "@pa mov.u32 a1, 0;\n" \
    "@pa mov.u32 a2, 0;\n" \
    "@pa mov.u32 a3, 0;\n" \
    "@pa mov.u32 a4, 0;\n" \
    "@pa mov.u32 a5, 0;\n" \
    "@pa mov.u32 a6, 0;\n" \
    "@pa mov.u32 a7, 0;\n" \
    "@pa add.s32 ps, ps, 128;\n" \
    "bra.uni KG0;\n" \
    "LG1:\n" \
    "and.b32 t0, m, 1024;\n" \
    "setp.ne.u32 pa, t0, 0;\n" \
    "and.b32 t0, mh, 1024;\n" \
    "setp.ne.u32 pb, t0, 0;\n" \
    "lop3.b32 t0, m, mh, 1024, 0x20;\n" \
    "setp.ne.u32 pc, t0, 0;\n" \
    "@pb st.volatile.shared.v4.u32 [sh], {a0,a1,a2,a3};\n" \
    "@pb st.volatile.shared.v4.u32 [sh+16512], {a4,a5,a6,a7};\n" \
    "cvt.rn.bf16x2.f32 t0, a1, a0;\n" \
    "cvt.rn.bf16x2.f32 t1, a3, a2;\n" \
    "cvt.rn.bf16x2.f32 t2, a5, a4;\n" \
    "cvt.rn.bf16x2.f32 t3, a7, a6;\n" \
    "@pc st.volatile.shared.v4.u32 [ps+73984], {t0,t1,t2,t3};\n" \
    "@pa mov.u32 a0, 0;\n" \
    "@pa mov.u32 a1, 0;\n" \
    "@pa mov.u32 a2, 0;\n" \
    "@pa mov.u32 a3, 0;\n" \
    "@pa mov.u32 a4, 0;\n" \
    "@pa mov.u32 a5, 0;\n" \
    "@pa mov.u32 a6, 0;\n" \
    "@pa mov.u32 a7, 0;\n" \
    "@pa add.s32 ps, ps, 128;\n" \
    "bra.uni KG1;\n" \
    "LG2:\n" \
    "and.b32 t0, m, 2048;\n" \
    "setp.ne.u32 pa, t0, 0;\n" \
    "and.b32 t0, mh, 2048;\n" \
    "setp.ne.u32 pb, t0, 0;\n" \
    "lop3.b32 t0, m, mh, 2048, 0x20;\n" \
    "setp.ne.u32 pc, t0, 0;\n" \
    "@pb st.volatile.shared.v4.u32 [sh], {a0,a1,a2,a3};\n" \
    "@pb st.volatile.shared.v4.u32 [sh+16512], {a4,a5,a6,a7};\n" \
    "cvt.rn.bf16x2.f32 t0, a1, a0;\n" \
    "cvt.rn.bf16x2.f32 t1, a3, a2;\n" \
    "cvt.rn.bf16x2.f32 t2, a5, a4;\n" \
    "cvt.rn.bf16x2.f32 t3, a7, a6;\n" \
    "@pc st.volatile.shared.v4.u32 [ps+73984], {t0,t1,t2,t3};\n" \
    "@pa mov.u32 a0, 0;\n" \
    "@pa mov.u32 a1, 0;\n" \
    "@pa mov.u32 a2, 0;\n" \
    "@pa mov.u32 a3, 0;\n" \
    "@pa mov.u32 a4, 0;\n" \
    "@pa mov.u32 a5, 0;\n" \
    "@pa mov.u32 a6, 0;\n" \
    "@pa mov.u32 a7, 0;\n" \
    "@pa add.s32 ps, ps, 128;\n" \
    "bra.uni KG2;\n" \
    "LG3:\n" \
    "and.b32 t0, m, 4096;\n" \
    "setp.ne.u32 pa, t0, 0;\n" \
    "and.b32 t0, mh, 4096;\n" \
    "setp.ne.u32 pb, t0, 0;\n" \
    "lop3.b32 t0, m, mh, 4096, 0x20;\n" \
    "setp.ne.u32 pc, t0, 0;\n" \
    "@pb st.volatile.shared.v4.u32 [sh], {a0,a1,a2,a3};\n" \
    "@pb st.volatile.shared.v4.u32 [sh+16512], {a4,a5,a6,a7};\n" \
    "cvt.rn.bf16x2.f32 t0, a1, a0;\n" \
    "cvt.rn.bf16x2.f32 t1, a3, a2;\n" \
    "cvt.rn.bf16x2.f32 t2, a5, a4;\n" \
    "cvt.rn.bf16x2.f32 t3, a7, a6;\n" \
    "@pc st.volatile.shared.v4.u32 [ps+73984], {t0,t1,t2,t3};\n" \
    "@pa mov.u32 a0, 0;\n" \
    "@pa mov.u32 a1, 0;\n" \
    "@pa mov.u32 a2, 0;\n" \
    "@pa mov.u32 a3, 0;\n" \
    "@pa mov.u32 a4, 0;\n" \
    "@pa mov.u32 a5, 0;\n" \
    "@pa mov.u32 a6, 0;\n" \
    "@pa mov.u32 a7, 0;\n" \
    "@pa add.s32 ps, ps, 128;\n" \
    "bra.uni KG3;\n" \
    "LG4:\n" \
    "and.b32 t0, m, 8192;\n" \
    "setp.ne.u32 pa, t0, 0;\n" \
    "and.b32 t0, mh, 8192;\n" \
    "setp.ne.u32 pb, t0, 0;\n" \
    "lop3.b32 t0, m, mh, 8192, 0x20;\n" \
    "setp.ne.u32 pc, t0, 0;\n" \
    "@pb st.volatile.shared.v4.u32 [sh], {a0,a1,a2,a3};\n" \
    "@pb st.volatile.shared.v4.u32 [sh+16512], {a4,a5,a6,a7};\n" \
    "cvt.rn.bf16x2.f32 t0, a1, a0;\n" \
    "cvt.rn.bf16x2.f32 t1, a3, a2;\n" \
    "cvt.rn.bf16x2.f32 t2, a5, a4;\n" \
    "cvt.rn.bf16x2.f32 t3, a7, a6;\n" \
    "@pc st.volatile.shared.v4.u32 [ps+73984], {t0,t1,t2,t3};\n" \
    "@pa mov.u32 a0, 0;\n" \
    "@pa mov.u32 a1, 0;\n" \
    "@pa mov.u32 a2, 0;\n" \
    "@pa mov.u32 a3, 0;\n" \
    "@pa mov.u32 a4, 0;\n" \
    "@pa mov.u32 a5, 0;\n" \
    "@pa mov.u32 a6, 0;\n" \
    "@pa mov.u32 a7, 0;\n" \
    "@pa add.s32 ps, ps, 128;\n" \
    "bra.uni KG4;\n" \
    "STAGE:\n" \
    "sub.s64 ad, tb, %3;\n" \
    "mul.wide.s32 as, first, 256;\n" \
    "add.s64 ad, ad, as;\n" \
    "add.s64 ad, ad, %4;\n" \
    "add.s64 ad, ad, 3072;\n" \
    "setp.gt.s32 pa, fr, 12;\n" \
    "@pa cp.async.cg.shared.global [sh+74112], [ad], 16;\n" \
    "bra.uni STAGED;\n" \
      \
    "SERVICE:\n" \
    "st.volatile.shared.u32 [%9+33024], %10;\n" \
    "st.volatile.shared.v4.u32 [%9+16384], {0,0,0,0};\n" \
    "st.volatile.shared.v4.u32 [%9+32896], {0,0,0,0};\n" \
    "bar.arrive 0, 1024;\n" \
    "mov.u32 %0, 0;\n" \
    "END:\n" \
    "}\n"

struct Params {
    const int* vals; const int* seg; const char* table; unsigned nnz4, lim; int P16, nact, B, n32;
    const char* out0; char* out; int n64, nnz, P; float invP4; unsigned item[133];
};
__device__ unsigned long long g_cover[80];

__device__ __forceinline__ uint32_t smem_u32(const void* p) { return (uint32_t)__cvta_generic_to_shared(p); }
__device__ __forceinline__ uint32_t pack2(float lo, float hi) { uint32_t r; asm("cvt.rn.bf16x2.f32 %0, %1, %2;" : "=r"(r) : "f"(hi), "f"(lo)); return r; }
__device__ __forceinline__ uint32_t add2(uint32_t a, uint32_t b) { uint32_t r; asm("add.rn.bf16x2 %0, %1, %2;" : "=r"(r) : "r"(a), "r"(b)); return r; }
__device__ __forceinline__ void accum(float (&a)[8], uint4 x) {
    a[0] += __uint_as_float(x.x << 16); a[1] += __uint_as_float(x.x & 0xffff0000u);
    a[2] += __uint_as_float(x.y << 16); a[3] += __uint_as_float(x.y & 0xffff0000u);
    a[4] += __uint_as_float(x.z << 16); a[5] += __uint_as_float(x.z & 0xffff0000u);
    a[6] += __uint_as_float(x.w << 16); a[7] += __uint_as_float(x.w & 0xffff0000u);
}
__device__ __noinline__ void generic_range(const Params& a, int half, int lo, int hi, int e, bool hasnext, uint32_t sh) {
    const int lane = threadIdx.x & 31;
    if (lo >= a.nnz || lane >= 8) return;
    const int col = half * 8 + lane;
    const uint4* o0 = (const uint4*)a.out0 + col; uint4* o = (uint4*)a.out + col; const uint4* tb = (const uint4*)a.table + col;
    int sc = lo > 0 ? a.seg[lo - 1] : -1;
    if (sc > a.seg[e - 1]) return;
    bool inhead = a.seg[lo] == sc;
    float s[8] = {0.f, 0.f, 0.f, 0.f, 0.f, 0.f, 0.f, 0.f};
    for (int p = lo;; p++) {
        const int sn = p < a.nnz ? a.seg[p] : a.B;
        const bool open = p >= hi && hasnext && sn == sc;
        if (open) {
            #pragma unroll
            for (int j = 0; j < 8; j++) {
                uint32_t t; int it = 0;
                do { asm volatile("ld.volatile.shared.u32 %0, [%1];" : "=r"(t) : "r"(sh + 512 + (j >> 2) * HEAD_BYTES + (j & 3) * 4) : "memory"); } while (t == 0xffffffffu && ++it < (1 << 28));
                s[j] += __uint_as_float(t);
            }
        }
        if (open || sn != sc) {
            if (p > lo) {
                if (!inhead) {
                    const uint4 r = o0[(size_t)sc * 16];
                    o[(size_t)sc * 16] = make_uint4(add2(pack2(s[0], s[1]), r.x), add2(pack2(s[2], s[3]), r.y), add2(pack2(s[4], s[5]), r.z), add2(pack2(s[6], s[7]), r.w));
                } else if (sh) {
                    asm volatile("st.volatile.shared.v4.f32 [%0], {%1,%2,%3,%4};" :: "r"(sh), "f"(s[0]), "f"(s[1]), "f"(s[2]), "f"(s[3]) : "memory");
                    asm volatile("st.volatile.shared.v4.f32 [%0], {%1,%2,%3,%4};" :: "r"(sh + HEAD_BYTES), "f"(s[4]), "f"(s[5]), "f"(s[6]), "f"(s[7]) : "memory");
                }
                inhead = false;
            }
            for (int t = sc + 1; t < sn; t++) o[(size_t)t * 16] = o0[(size_t)t * 16];
            if (p >= hi || p >= e) return;
            sc = sn;
            #pragma unroll
            for (int j = 0; j < 8; j++) s[j] = 0.f;
        }
        accum(s, tb[(size_t)a.vals[p] * 16]);
    }
}

template<bool BYSM>
__global__ void __launch_bounds__(1024, 1) emb_kernel(const __grid_constant__ Params a) {
    extern __shared__ __align__(16) char sm[];
    int status; unsigned item;
    if (BYSM) {
        unsigned smid; asm volatile("mov.u32 %0, %%smid;" : "=r"(smid));
        item = a.item[min(smid, 132u + (threadIdx.x >> 10))];
    } else item = (blockIdx.x >> 1) * a.P * 4 + (blockIdx.x & 1);
    asm volatile(FAST_PTX : "=&r"(status) : "l"(a.vals), "l"(a.seg), "l"(a.table), "l"(a.out0), "l"(a.out), "r"(a.n32), "r"(a.B), "r"(a.P16),
                 "r"(smem_u32(sm)), "r"(item), "r"(a.nnz4), "r"(a.n64), "r"(a.nact), "r"(a.lim) : "memory");
    item = *(const unsigned*)(sm + REF_OFF);
    if (status) {
        const int b = item >> 2, e = min(a.nnz, b + a.P), lo = b + (threadIdx.x >> 5) * 4 * CQ;
        if (lo < e + CQ) generic_range(a, item & 1, lo, lo + 4 * CQ, e, lo + 3 * CQ < e, smem_u32(sm) + threadIdx.x * 16);
    }
    if (BYSM && threadIdx.x >= 992) {
        __syncwarp();
        const int lane = threadIdx.x & 31;
        const unsigned id = __float2uint_rn((float)(item & ~3u) * a.invP4) * 2 + (item & 1);
        bool bad = false;
        if (lane < 5) {
            const unsigned long long add = (1ull << 56) + ((int)(id >> 5) == lane ? (1ull << 48) + (1ull << (id & 31)) : 0ull);
            const unsigned long long now = atomicAdd(&g_cover[lane * 16], add) + add;
            if ((now >> 56) == 132) { g_cover[lane * 16] = 0; bad = now != (lane < 4 ? 0x84200000ffffffffull : 0x840400000000000full); }
        }
        const unsigned redo = __ballot_sync(~0u, bad);
        if (redo) for (int i = 0; i < 132; i++) if (redo >> (i >> 5) & 1) {
            const int b = (i >> 1) * a.P, e = min(a.nnz, b + a.P);
            generic_range(a, i & 1, b, e, e, false, 0);
        }
    }
}

__global__ void emb_kernel_huge(const __grid_constant__ Params a) {
    const long long wid = (long long)blockIdx.x * (blockDim.x >> 5) + (threadIdx.x >> 5), lo = (wid >> 1) * 64;
    if (lo < a.nnz) { const int hi = (int)min(lo + 64, (long long)a.nnz); generic_range(a, (int)(wid & 1), (int)lo, hi, hi, false, 0); }
}

extern "C" void kernel_launch(void* const* d_in, const int* in_sizes, int n_in, void* d_out, int out_size) {
    static int sms = 0;
    if (!sms) {
        int dev = 0; cudaGetDevice(&dev);
        cudaDeviceGetAttribute(&sms, cudaDevAttrMultiProcessorCount, dev);
        cudaFuncSetAttribute(emb_kernel<true>, cudaFuncAttributeMaxDynamicSharedMemorySize, SMEM_BYTES);
        cudaFuncSetAttribute(emb_kernel<false>, cudaFuncAttributeMaxDynamicSharedMemorySize, SMEM_BYTES);
    }
    Params a = {};
    a.vals = (const int*)d_in[0]; a.seg = (const int*)d_in[1]; a.table = (const char*)d_in[2]; a.out0 = (const char*)d_in[3]; a.out = (char*)d_out;
    a.nnz = in_sizes[0]; a.B = out_size / 128;
    if (a.nnz == 0) { cudaMemcpyAsync(d_out, d_in[3], (size_t)out_size * 2, cudaMemcpyDeviceToDevice, cudaStreamPerThread); return; }
    if (a.nnz >= (1 << 28) || (((uintptr_t)a.vals | (uintptr_t)a.seg) & 15)) { emb_kernel_huge<<<(a.nnz + 255u) / 256u, 256, 0, cudaStreamPerThread>>>(a); return; }
    const bool bysm = sms == 132 && a.nnz <= 66 * MAXP;
    const int nchunk = sms == 132 ? 64 : (sms > 1 ? sms / 2 : 1);
    int P = ((a.nnz + nchunk - 1) / nchunk + 3) & ~3; if (P > MAXP) P = MAXP;
    a.P = P; a.P16 = 4 * P - 16; a.invP4 = 1.0f / (4.0f * P); a.nact = (P + 2 * CQ - 1) / CQ * 8;
    a.nnz4 = 4u * a.nnz; a.n32 = 4 * a.nnz - 32; a.n64 = 4 * a.nnz - 64; a.lim = (a.nnz4 - 4) & ~15u;
    int cnt[2] = {0, 0};
    for (int s = 0; s < 132; s++) {
        const int t = s >> 1;
        if (t == 60 || t == 61) { a.item[s] = (64 + (s & 1)) * P * 4 + (t & 1); continue; }
        const int half = (int)((0x08f1e3c78e8e8e8eull >> (t > 61 ? t - 2 : t)) & 1);
        a.item[s] = cnt[half]++ * P * 4 + half;
    }
    a.item[132] = 100 * P * 4;
    if (bysm) emb_kernel<true><<<132, 1024, SMEM_BYTES, cudaStreamPerThread>>>(a);
    else emb_kernel<false><<<2 * ((a.nnz + P - 1) / P), 1024, SMEM_BYTES, cudaStreamPerThread>>>(a);
}
```
